```python
import torch

def _softmax(x, axis=-1):
    return torch.softmax(x, dim=axis)
def _gelu(x):
    return torch.nn.functional.gelu(x, approximate="tanh")
def _silu(x):
    return torch.nn.functional.silu(x)
def _sigmoid(x):
    return torch.sigmoid(x)
def _layernorm(x, axis=-1, eps=1e-5):
    m = x.mean(dim=axis, keepdim=True)
    v = x.var(dim=axis, keepdim=True, unbiased=False)
    return (x - m) / torch.sqrt(v + eps)
def _scatter_add(tgt, idx, src, axis=0):
    return tgt.clone().index_add_(axis, idx, src)
def _segment_sum(src, seg, n):
    out = torch.zeros((n,) + src.shape[1:], dtype=src.dtype)
    return out.index_add_(0, seg, src)
def _pad(x, pw):
    flat = tuple(v for pair in reversed(pw) for v in pair)
    return torch.nn.functional.pad(x, flat)

kernel_name = 'recurrent_scan__gqa_block_cached__glu_gated_reglu__decode'

def setup_inputs():

    _w = (lambda a: (lambda t: t.to(torch.bfloat16) if t.is_floating_point() else t)(torch.as_tensor(a)))
    def _A_setup():
        B, Sq, D = 4, 1, 576
        Hq, Hkv, Sk, Dh = 32, 16, 8192, 128
        assert Hq % Hkv == 0, (Hq, Hkv)
        return {
            "x": _w((lambda *s: torch.randn(*s, dtype=torch.bfloat16) * 0.2)(B, Sq, D)),
            "k_cache": _w((lambda *s: torch.randn(*s, dtype=torch.bfloat16) * 1.6)(B, Hkv, Sk, Dh)),
            "v_cache": _w((lambda *s: torch.randn(*s, dtype=torch.bfloat16) * 1.6)(B, Hkv, Sk, Dh)),
            "wq": _w((lambda *s: torch.randn(*s, dtype=torch.bfloat16) * 1.6)(D, Hq * Dh) * (D ** -0.5)),
            "wo": _w((lambda *s: torch.randn(*s, dtype=torch.bfloat16) * 1.6)(Hq * Dh, D) * ((Hq * Dh) ** -0.5)),
        }
    _A_in = _A_setup()

    def _B_setup():
        B, S, D, F = 4, 1, 576, 4608
        return {
            "x": _w((lambda *s: torch.randn(*s, dtype=torch.bfloat16) * 0.2)(B, S, D)),
            "W_gate": _w((lambda *s: torch.randn(*s, dtype=torch.bfloat16) * 0.8)(D, F) * (2.0 / D) ** 0.5),
            "W_up": _w((lambda *s: torch.randn(*s, dtype=torch.bfloat16) * 0.8)(D, F) * (2.0 / D) ** 0.5),
            "W_down": _w((lambda *s: torch.randn(*s, dtype=torch.bfloat16) * 0.8)(F, D) * (1.0 / F) ** 0.5),
        }
    _B_in = _B_setup()

    return {
        "A_x": _A_in["x"],
        "A_k_cache": _A_in["k_cache"],
        "A_v_cache": _A_in["v_cache"],
        "A_wq": _A_in["wq"],
        "A_wo": _A_in["wo"],
        "B_x": _B_in["x"],
        "B_W_gate": _B_in["W_gate"],
        "B_W_up": _B_in["W_up"],
        "B_W_down": _B_in["W_down"],
    }

def reference(A_x, A_k_cache, A_v_cache, A_wq, A_wo, B_x, B_W_gate, B_W_up, B_W_down):
    def _A_ref(x, k_cache, v_cache, wq, wo):
        B, Sq, D = x.shape
        Hq, Dh = 32, 128
        Hkv = k_cache.shape[1]
        rep = Hq // Hkv
        q = (lambda x, *d: x.permute(*d))((x @ wq).reshape(B, Sq, Hq, Dh), 0, 2, 1, 3)
        k = (lambda x, n, axis: torch.repeat_interleave(x, n, dim=axis))(k_cache, rep, axis=1)
        v = (lambda x, n, axis: torch.repeat_interleave(x, n, dim=axis))(v_cache, rep, axis=1)
        scores = torch.einsum("bhqd,bhkd->bhqk", q, k) * (Dh ** -0.5)
        p = _softmax(scores, axis=-1)
        o = torch.einsum("bhqk,bhkd->bhqd", p, v)
        return (lambda x, *d: x.permute(*d))(o, 0, 2, 1, 3).reshape(B, Sq, Hq * Dh) @ wo

    def _B_ref(x, W_gate, W_up, W_down):
        gate = torch.einsum("bsd,df->bsf", x, W_gate)
        up = torch.einsum("bsd,df->bsf", x, W_up)
        gate = gate * (lambda x, dt: x.to(dt))(gate > 0, gate.dtype)
        h = gate * up
        return torch.einsum("bsf,fd->bsd", h, W_down)

    x = A_x
    xn = _layernorm(x, axis=-1)
    s = _A_ref(xn, A_k_cache, A_v_cache, A_wq, A_wo)
    g = _silu(_B_ref(xn, B_W_gate, B_W_up, B_W_down))
    return x + s * g
```

```cpp
#include <cuda_runtime.h>
#include <cuda_bf16.h>
#include <stdint.h>

namespace rk {

constexpr int kB = 4, kD = 576, kHQ = 32, kHKV = 16, kSK = 8192, kDH = 128, kF = 4608;
constexpr int kTile = 64;
constexpr int kHalfBytes = kTile * kDH * 2;
constexpr int kVisPerPair = kSK / kTile;
constexpr int kNPair = kB * kHKV;
constexpr int kNVis = kNPair * kVisPerPair;
constexpr int kVisShift = 13;
constexpr int NA = 3;
constexpr int NS = 2;
constexpr int NW = 9;
constexpr int kThreads = (NA + NW) * 32;
constexpr int kWThreads = NW * 32;
constexpr int kNUnitA = 128;
constexpr int kNUnitF = 144;
constexpr int kNFin = 72;
constexpr int kNPart = kNUnitA + kNUnitF;
constexpr int kCritHkv = 13;
constexpr int kUrgentHkv = 12;
constexpr int kEagerHkv = 14;

constexpr int kXnStride = 584;
constexpr int kActStride = 40;
constexpr int kRowBytes = kD * 2;
constexpr int kRowStride = kRowBytes + 16;
constexpr int SM_SLOTS = 0;
constexpr int SM_Q = SM_SLOTS + NS * 2 * kHalfBytes;
constexpr int SM_WD = SM_Q + NS * 1536;
constexpr int SM_WO = SM_WD + 32 * kRowStride;
constexpr int SM_RED = SM_WO + 32 * kRowStride;
constexpr int SM_XN = SM_RED + (512 + NW * 256 + 264) * 4;
constexpr int SM_ACT = SM_XN + kB * kXnStride * 2;
constexpr int SM_BAR = SM_ACT + 3 * kB * kActStride * 2;
constexpr int kNBar = 2 * NA + 4;
constexpr int SM_MISC = SM_BAR + kNBar * 8;
constexpr int SM_TOTAL = SM_MISC + 32;
static_assert(SM_TOTAL <= 232448, "shared memory budget");

__device__ unsigned int g_ticket;
__device__ ulonglong2 g_qx[kB * kHQ * 32];
__device__ float4 g_apart[kNPair * 2 * 4 * kVisPerPair * 8];
__device__ float2 g_aml[kNPair * 2 * kVisPerPair];
__device__ float4 g_fin[kNFin * kNPart * 8];


struct Params {
    const __nv_bfloat16 *x, *k, *v, *wq, *wo, *wg, *wu, *wd;
    __nv_bfloat16* out;
};

__device__ __forceinline__ uint32_t smem_u32(const void* p) { return (uint32_t)__cvta_generic_to_shared(p); }
__device__ __forceinline__ void mbar_init(uint32_t a, uint32_t c) {
    asm volatile("mbarrier.init.shared::cta.b64 [%0], %1;" ::"r"(a), "r"(c) : "memory");
}
__device__ __forceinline__ void mbar_expect(uint32_t a, uint32_t bytes) {
    asm volatile("mbarrier.arrive.expect_tx.shared::cta.b64 _, [%0], %1;" ::"r"(a), "r"(bytes) : "memory");
}
__device__ __forceinline__ void mbar_arrive(uint32_t a) {
    asm volatile("mbarrier.arrive.shared::cta.b64 _, [%0];" ::"r"(a) : "memory");
}
__device__ __forceinline__ bool mbar_try(uint32_t a, uint32_t parity) {
    uint32_t ok;
    asm volatile(
        "{.reg .pred p; mbarrier.try_wait.parity.shared::cta.b64 p, [%1], %2; selp.u32 %0,1,0,p;}"
        : "=r"(ok) : "r"(a), "r"(parity) : "memory");
    return ok != 0;
}
__device__ __forceinline__ bool mbar_test(uint32_t a, uint32_t parity) {
    uint32_t ok;
    asm volatile(
        "{.reg .pred p; mbarrier.test_wait.parity.shared::cta.b64 p, [%1], %2; selp.u32 %0,1,0,p;}"
        : "=r"(ok) : "r"(a), "r"(parity) : "memory");
    return ok != 0;
}
__device__ __forceinline__ bool timed_out(uint32_t t0, volatile int* dead) {
    if ((int)((uint32_t)clock() - t0) < 0) *dead = 1;
    return *dead != 0;
}
__device__ __forceinline__ void mbar_wait(uint32_t a, uint32_t parity, volatile int* dead) {
    if (mbar_try(a, parity)) return;
    const uint32_t t0 = (uint32_t)clock();
    while (!mbar_try(a, parity))
        if (timed_out(t0, dead)) return;
}
__device__ __forceinline__ bool poll_backoff(uint32_t t0, unsigned ns, volatile int* dead) {
    __nanosleep(ns);
    return timed_out(t0, dead);
}
__device__ __forceinline__ void bulk_load(uint32_t dst, const void* src, uint32_t bytes, uint32_t bar, uint64_t pol) {
    asm volatile(
        "cp.async.bulk.shared::cluster.global.mbarrier::complete_tx::bytes.L2::cache_hint [%0], [%1], %2, [%3], %4;"
        ::"r"(dst), "l"(src), "r"(bytes), "r"(bar), "l"(pol) : "memory");
}
__device__ __forceinline__ uint4 ldg_stream(const void* p) {
    uint4 r;
    asm volatile("ld.global.nc.L1::no_allocate.v4.u32 {%0,%1,%2,%3}, [%4];"
                 : "=r"(r.x), "=r"(r.y), "=r"(r.z), "=r"(r.w) : "l"(p));
    return r;
}
__device__ __forceinline__ uint4 ld_rlx4(const void* p) {
    uint4 r;
    asm volatile("ld.relaxed.gpu.global.v4.u32 {%0,%1,%2,%3}, [%4];"
                 : "=r"(r.x), "=r"(r.y), "=r"(r.z), "=r"(r.w) : "l"(p) : "memory");
    return r;
}
__device__ __forceinline__ uint2 ld_rlx2(const void* p) {
    uint2 r;
    asm volatile("ld.relaxed.gpu.global.v2.u32 {%0,%1}, [%2];" : "=r"(r.x), "=r"(r.y) : "l"(p) : "memory");
    return r;
}
__device__ __forceinline__ ulonglong2 ld_rlx2x64(const void* p) {
    ulonglong2 r;
    asm volatile("ld.relaxed.gpu.global.v2.u64 {%0,%1}, [%2];" : "=l"(r.x), "=l"(r.y) : "l"(p) : "memory");
    return r;
}
__device__ __forceinline__ void st_rlx4(void* p, uint32_t a, uint32_t b, uint32_t c, uint32_t d) {
    asm volatile("st.relaxed.gpu.global.v4.u32 [%0], {%1,%2,%3,%4};" ::"l"(p), "r"(a), "r"(b), "r"(c), "r"(d) : "memory");
}
__device__ __forceinline__ void st_rlx2(void* p, uint32_t a, uint32_t b) {
    asm volatile("st.relaxed.gpu.global.v2.u32 [%0], {%1,%2};" ::"l"(p), "r"(a), "r"(b) : "memory");
}
__device__ __forceinline__ void st_rlx64(void* p, unsigned long long v) {
    asm volatile("st.relaxed.gpu.global.u64 [%0], %1;" ::"l"(p), "l"(v) : "memory");
}
__device__ __forceinline__ unsigned int take_ticket() {
    unsigned int v;
    asm volatile(
        "{.reg .u32 l; .reg .u64 a; mov.u32 l, %%laneid; mad.wide.u32 a, l, 4, %1;\n"
        " atom.relaxed.gpu.global.add.u32 %0, [a], 1;}"
        : "=r"(v) : "l"(&g_ticket) : "memory");
    return v;
}
__device__ __forceinline__ void mma16816(float (&c)[4], uint32_t a0, uint32_t a1, uint32_t a2, uint32_t a3,
                                         uint32_t b0, uint32_t b1) {
    asm("mma.sync.aligned.m16n8k16.row.col.f32.bf16.bf16.f32 {%0,%1,%2,%3}, {%4,%5,%6,%7}, {%8,%9}, {%0,%1,%2,%3};"
        : "+f"(c[0]), "+f"(c[1]), "+f"(c[2]), "+f"(c[3])
        : "r"(a0), "r"(a1), "r"(a2), "r"(a3), "r"(b0), "r"(b1));
}
__device__ __forceinline__ float ex2(float x) {
    float y;
    asm("ex2.approx.ftz.f32 %0, %1;" : "=f"(y) : "f"(x));
    return y;
}
__device__ __forceinline__ uint32_t pack_bf16(float lo, float hi) {
    __nv_bfloat162 v = __floats2bfloat162_rn(lo, hi);
    return *reinterpret_cast<uint32_t*>(&v);
}
__device__ __forceinline__ float bf16r(float x) { return __bfloat162float(__float2bfloat16_rn(x)); }
__device__ __forceinline__ uint32_t tagf(float x, uint32_t tag2) { return (__float_as_uint(x) & ~3u) | tag2; }
__device__ __forceinline__ bool tag_ok4(const uint4& v, uint32_t tag2) {
    return (((v.x ^ tag2) | (v.y ^ tag2) | (v.z ^ tag2) | (v.w ^ tag2)) & 3u) == 0;
}
__device__ __forceinline__ uint32_t word_of(const uint4& v, int i) {
    return i == 0 ? v.x : i == 1 ? v.y : i == 2 ? v.z : v.w;
}
__device__ __forceinline__ void wbar() { asm volatile("bar.sync 1, 288;" ::: "memory"); }

struct WRegs { uint4 r[2][4]; };

__device__ __forceinline__ void load_colunit(WRegs& L, const __nv_bfloat16* W, int n, int unit, int w, int g, int t) {
    const __nv_bfloat16* p = W + (size_t)(64 * w + 16 * (g >> 2) + 2 * t) * n + 32 * unit + 8 * (g & 3);
#pragma unroll
    for (int uu = 0; uu < 2; uu++) {
        L.r[uu][0] = ldg_stream(p + (size_t)(32 * uu + 0) * n);
        L.r[uu][1] = ldg_stream(p + (size_t)(32 * uu + 1) * n);
        L.r[uu][2] = ldg_stream(p + (size_t)(32 * uu + 8) * n);
        L.r[uu][3] = ldg_stream(p + (size_t)(32 * uu + 9) * n);
    }
}
__device__ __forceinline__ void issue_rowunit(uint32_t dst, const __nv_bfloat16* W, int unit, uint32_t bar, int lane,
                                              uint64_t pol) {
    if (lane == 0) mbar_expect(bar, 32 * kRowBytes);
    __syncwarp();
    bulk_load(dst + lane * kRowStride, W + (size_t)(32 * unit + lane) * kD, kRowBytes, bar, pol);
}
__device__ __forceinline__ void unit_mma(float (&acc)[8][4], const WRegs& L, const uint32_t (&a0)[2], const uint32_t (&a2)[2]) {
#pragma unroll
    for (int j = 0; j < 8; j++) { acc[j][0] = acc[j][1] = acc[j][2] = acc[j][3] = 0.f; }
#pragma unroll
    for (int uu = 0; uu < 2; uu++) {
#pragma unroll
        for (int j = 0; j < 8; j++) {
            const uint32_t sel = (j & 1) ? 0x7632u : 0x5410u;
            const uint32_t b0 = __byte_perm(word_of(L.r[uu][0], j >> 1), word_of(L.r[uu][1], j >> 1), sel);
            const uint32_t b1 = __byte_perm(word_of(L.r[uu][2], j >> 1), word_of(L.r[uu][3], j >> 1), sel);
            mma16816(acc[j], a0[uu], 0u, a2[uu], 0u, b0, b1);
        }
    }
}
__device__ __forceinline__ void colunit_partial(const WRegs& L, const __nv_bfloat16* xn, float* redw, int w, int g, int t) {
    uint32_t a0[2], a2[2];
    const __nv_bfloat16* ap = xn + (g & 3) * kXnStride + 64 * w + 16 * (g >> 2) + 2 * t;
#pragma unroll
    for (int uu = 0; uu < 2; uu++) {
        a0[uu] = *reinterpret_cast<const uint32_t*>(ap + 32 * uu);
        a2[uu] = *reinterpret_cast<const uint32_t*>(ap + 32 * uu + 8);
    }
    float acc[8][4];
    unit_mma(acc, L, a0, a2);
    const bool hi = (t & 2) != 0;
    float r[4][2];
#pragma unroll
    for (int jj = 0; jj < 4; jj++) {
#pragma unroll
        for (int c = 0; c < 2; c++) {
            const float send = hi ? acc[jj][c] : acc[jj + 4][c];
            const float keep = hi ? acc[jj + 4][c] : acc[jj][c];
            r[jj][c] = keep + __shfl_xor_sync(0xffffffffu, send, 18);
        }
    }
    if ((g >> 2) == (t >> 1)) {
        float* dst = redw + (g & 3) * 32 + 16 * (t & 1) + 4 * (t >> 1);
        *reinterpret_cast<float4*>(dst) = make_float4(r[0][0], r[1][0], r[2][0], r[3][0]);
        *reinterpret_cast<float4*>(dst + 8) = make_float4(r[0][1], r[1][1], r[2][1], r[3][1]);
    }
}
__device__ __forceinline__ float4* fin_slot(int line, int w, int pidx, int lane) {
    return g_fin + ((size_t)((line >> 1) * 18 + 2 * w + (line & 1)) * kNPart + pidx) * 8 + (lane & 7);
}
struct BFrag { uint32_t b[2][8][2]; };
__device__ __forceinline__ void rowunit_load(BFrag& F, const unsigned char* ws, int w, int lane) {
    const unsigned char* wp = ws + (2 * (lane & 3)) * kRowStride + (8 * w + (lane >> 2)) * 16;
#pragma unroll
    for (int uu = 0; uu < 2; uu++) {
        const uint4 r0 = *reinterpret_cast<const uint4*>(wp + (16 * uu + 0) * kRowStride);
        const uint4 r1 = *reinterpret_cast<const uint4*>(wp + (16 * uu + 1) * kRowStride);
        const uint4 r2 = *reinterpret_cast<const uint4*>(wp + (16 * uu + 8) * kRowStride);
        const uint4 r3 = *reinterpret_cast<const uint4*>(wp + (16 * uu + 9) * kRowStride);
#pragma unroll
        for (int j = 0; j < 8; j++) {
            const uint32_t sel = (j & 1) ? 0x7632u : 0x5410u;
            F.b[uu][j][0] = __byte_perm(word_of(r0, j >> 1), word_of(r1, j >> 1), sel);
            F.b[uu][j][1] = __byte_perm(word_of(r2, j >> 1), word_of(r3, j >> 1), sel);
        }
    }
}
__device__ __forceinline__ void rowunit_publish(const BFrag& F, const __nv_bfloat16* act, float* stage, int pidx,
                                                uint32_t tag2, int w, int lane) {
    const int g = lane >> 2, t = lane & 3;
    const __nv_bfloat16* ap = act + (g & 3) * kActStride + 2 * t;
    float acc[8][4];
#pragma unroll
    for (int j = 0; j < 8; j++) { acc[j][0] = acc[j][1] = acc[j][2] = acc[j][3] = 0.f; }
#pragma unroll
    for (int uu = 0; uu < 2; uu++) {
        const uint32_t v0 = *reinterpret_cast<const uint32_t*>(ap + 16 * uu);
        const uint32_t v2 = *reinterpret_cast<const uint32_t*>(ap + 16 * uu + 8);
#pragma unroll
        for (int j = 0; j < 8; j++) mma16816(acc[j], v0, 0u, v2, 0u, F.b[uu][j][0], F.b[uu][j][1]);
    }
    if (g < 4) {
        float4* sp = reinterpret_cast<float4*>(stage + g * 64 + 16 * t);
#pragma unroll
        for (int c = 0; c < 2; c++) {
            sp[2 * c] = make_float4(acc[0][c], acc[1][c], acc[2][c], acc[3][c]);
            sp[2 * c + 1] = make_float4(acc[4][c], acc[5][c], acc[6][c], acc[7][c]);
        }
    }
    __syncwarp();
#pragma unroll
    for (int i = 0; i < 2; i++) {
        const int line = 4 * i + (lane >> 3);
        const float4 v = *reinterpret_cast<const float4*>(stage + line * 32 + 4 * (lane & 7));
        st_rlx4(fin_slot(line, w, pidx, lane), tagf(v.x, tag2), tagf(v.y, tag2), tagf(v.z, tag2), tagf(v.w, tag2));
    }
    __syncwarp();
}

__global__ void __launch_bounds__(kThreads, 1) fused_decode_kernel(const Params P) {
    extern __shared__ __align__(1024) unsigned char smem[];
    const int tid = threadIdx.x, warp = tid >> 5, lane = tid & 31;
    const int g = lane >> 2, t = lane & 3;
    const int G = gridDim.x, c = blockIdx.x;
    const uint32_t sbase = smem_u32(smem);
    const uint32_t bar0 = sbase + SM_BAR;
    const uint32_t dnbar = bar0 + 8 * (2 * NA), wobar = dnbar + 8, cbar = dnbar + 16, mlbar = dnbar + 24;
    volatile uint32_t* s_tag = reinterpret_cast<volatile uint32_t*>(smem + SM_MISC);
    unsigned int* s_exh = reinterpret_cast<unsigned int*>(smem + SM_MISC + 4);
    volatile int* dead = reinterpret_cast<volatile int*>(smem + SM_MISC + 8);
    unsigned int* s_dnfree = reinterpret_cast<unsigned int*>(smem + SM_MISC + 12);
    const bool hasA = c < kNUnitA;
    const int hkv = c >> 3;
    const bool critical = hasA && hkv >= kCritHkv;
    const bool twoF = G + c < kNUnitF;
    if (warp >= NA) {
        const int w = warp - NA, wt = tid - NA * 32;
        unsigned int tk = 0;
        if (wt == kWThreads - 32) asm volatile("ld.relaxed.gpu.global.u32 %0, [%1];" : "=r"(tk) : "l"(&g_ticket) : "memory");
        WRegs L;
        load_colunit(L, hasA ? P.wq : P.wg, hasA ? kHQ * kDH : kF, c, w, g, t);
        unsigned long long* qdst = reinterpret_cast<unsigned long long*>(g_qx) +
                                   (((wt >> 4) & 3) * kHQ + (c >> 2)) * 64 + 16 * (c & 3) + (wt & 15);
        if (hasA && wt < 64) st_rlx64(qdst, 0ull);
        __nv_bfloat16* xn = reinterpret_cast<__nv_bfloat16*>(smem + SM_XN);
        __nv_bfloat16* act = reinterpret_cast<__nv_bfloat16*>(smem + SM_ACT);
        float* red = reinterpret_cast<float*>(smem + SM_RED);
        if (wt == kWThreads - 32) {
            mbar_init(dnbar, 1);
            mbar_init(wobar, 1);
            mbar_init(cbar, 1);
            mbar_init(mlbar, 1);
            *s_exh = 0;
            *dead = 0;
            *s_dnfree = 0;
            asm volatile("fence.mbarrier_init.release.cluster;" ::: "memory");
            asm volatile("fence.proxy.async.shared::cta;" ::: "memory");
            *s_tag = (tk >> kVisShift) + 1u;
        }
        if (w == NW - 1) {
            __syncwarp();
            asm volatile("bar.arrive 3, 64;" ::: "memory");
        }
        asm volatile("bar.sync 0, %0;" ::"n"(kThreads) : "memory");
        const uint32_t tag32 = *s_tag, tag2 = tag32 & 3u;
        float xres = 0.f;
        bool first = true;
        const uint32_t stale = (tag2 + 3u) & 3u;
        if (hasA) {
            if (wt < 64) {
                const int ph = ((wt >> 4) * kHKV + hkv) * 2 + ((c >> 2) & 1);
                st_rlx4(reinterpret_cast<float4*>(g_aml + (size_t)ph * kVisPerPair) + (c & 3) * 16 + (wt & 15), stale, stale, stale, stale);
            }
            if (hkv >= kEagerHkv) {
                const int ph = ((kB - 1) * kHKV + hkv) * 2 + ((c >> 2) & 1);
                float4* ap = g_apart + ((size_t)ph * 4 + (c & 3)) * kVisPerPair * 8;
                for (int i = wt; i < kVisPerPair * 8; i += kWThreads) st_rlx4(ap + i, stale, stale, stale, stale);
            }
            __threadfence();
        }
        const int lastjob = twoF ? 4 : 2;
#pragma unroll 1
        for (int job = hasA ? 0 : 1; job <= lastjob; job++) {
            const bool second = job != 0 && (job & 1) == 0;
            colunit_partial(L, xn, red + (second ? NW * 128 : 0) + w * 128, w, g, t);
            if ((job & 1) == 0) {
                wbar();
                if (wt < 64) {
                    float ga = 0.f, gb = 0.f, ua = 0.f, ub = 0.f;
#pragma unroll
                    for (int i = 0; i < NW; i++) {
                        const float2 vg2 = *reinterpret_cast<const float2*>(red + i * 128 + 2 * wt);
                        const float2 vu2 = *reinterpret_cast<const float2*>(red + NW * 128 + i * 128 + 2 * wt);
                        ga += vg2.x; gb += vg2.y; ua += vu2.x; ub += vu2.y;
                    }
                    if (job == 0) {
                        st_rlx64(qdst, ((unsigned long long)tag32 << 32) | pack_bf16(ga, gb));
                    } else {
                        ga = bf16r(ga); gb = bf16r(gb); ua = bf16r(ua); ub = bf16r(ub);
                        ga = ga > 0.f ? ga : 0.f;
                        gb = gb > 0.f ? gb : 0.f;
                        *reinterpret_cast<uint32_t*>(act + ((job == 4 ? 2 * kB : 0) + (wt >> 4)) * kActStride + 2 * (wt & 15)) =
                            pack_bf16(ga * ua, gb * ub);
                    }
                }
            }
            if (job < lastjob) load_colunit(L, (job & 1) ? P.wu : P.wg, kF, job >= 2 ? G + c : c, w, g, t);
            if (first) {
                first = false;
                if (c < kNFin && w == 0) xres = __bfloat162float(P.x[c * 32 + lane]);
                if (w == NW - 1 && (critical || twoF)) {
                    uint64_t pol;
                    asm volatile("createpolicy.fractional.L2::evict_first.b64 %0, 1.0;" : "=l"(pol));
                    issue_rowunit(sbase + SM_WD, P.wd, twoF ? G + c : c, dnbar, lane, pol);
                    if (critical) issue_rowunit(sbase + SM_WO, P.wo, c, wobar, lane, pol);
                }
            }
            if ((job & 1) == 0) wbar();
        }
        {
#pragma unroll 1
            for (int k = hasA ? 0 : 1; k < (twoF ? 3 : 2); k++) {
                const int pidx = k == 0 ? c : kNUnitA + (k == 2 ? G + c : c);
#pragma unroll
                for (int i = 0; i < 2; i++) st_rlx4(fin_slot(4 * i + (lane >> 3), w, pidx, lane), stale, stale, stale, stale);
            }
        }
        int b = hasA ? 0 : kB;
        int dn_left = twoF ? 2 : 1;
        bool wo_done = !hasA, warmed = false, fine = false, wo_loaded = false;
        BFrag F;
        uint4 ov[4];
        uint32_t okm = 0;
        const uint32_t t0 = (uint32_t)clock();
        while (true) {
            const uint32_t dn_phase = (twoF && dn_left == 1) ? 1u : 0u;
            int task;
            {
                const bool give_up = *dead != 0;
                if (!warmed || (dn_left == 0 && wo_done)) task = 3;
                else if (b == kB && !wo_done && (mbar_test(wobar, 0) || give_up)) task = 1;
                else if (dn_left > 0 && (mbar_test(dnbar, dn_phase) || give_up)) task = 2;
                else task = b < kB ? 0 : 4;
                task = __shfl_sync(0xffffffffu, task, 0);
            }
            if (task == 0) {
                const int ph = (b * kHKV + hkv) * 2 + ((c >> 2) & 1);
                float* cb = red + (b & 1) * 256;
                float* wg = red + 512 + NW * 256 + (b & 1) * 132;
                if (b == kB - 1 && !wo_loaded && __all_sync(0xffffffffu, mbar_test(wobar, 0))) {
                    rowunit_load(F, smem + SM_WO, w, lane);
                    wo_loaded = true;
                }
                if (w == NW - 1) {
                    const float2* ml = g_aml + (size_t)ph * kVisPerPair;
                    const bool urgent = b == kB - 1 && hkv >= kUrgentHkv;
                    if (!fine) {
                        const uint2 v = ld_rlx2(ml + (urgent ? kVisPerPair / 2 : kVisPerPair - 1));
                        fine = ((v.x ^ tag2) & 3u) == 0;
                        if (!fine) fine = poll_backoff(t0, 400, dead);
                        fine = __any_sync(0xffffffffu, fine);
                        if (fine && lane == 0) mbar_arrive(cbar);
                        okm = 0;
                        continue;
                    }
#pragma unroll
                    for (int i = 0; i < 4; i++) {
                        if (!(okm >> i & 1)) {
                            const uint2 v = ld_rlx2(ml + lane + 32 * i);
                            ov[i].x = v.x;
                            ov[i].y = v.y;
                        }
                    }
#pragma unroll
                    for (int i = 0; i < 4; i++)
                        if ((((ov[i].x ^ tag2) | (ov[i].y ^ tag2)) & 3u) == 0) okm |= 1u << i;
                    if (!__all_sync(0xffffffffu, okm == 15u)) {
                        if (!__any_sync(0xffffffffu, poll_backoff(t0, urgent ? 30 : 400, dead))) continue;
                    }
                    float M = fmaxf(fmaxf(__uint_as_float(ov[0].x), __uint_as_float(ov[1].x)),
                                    fmaxf(__uint_as_float(ov[2].x), __uint_as_float(ov[3].x)));
                    {
                        int k = __float_as_int(M);
                        k ^= (k >> 31) & 0x7fffffff;
                        k = __reduce_max_sync(0xffffffffu, k);
                        k ^= (k >> 31) & 0x7fffffff;
                        M = __int_as_float(k);
                    }
                    float Ls = 0.f;
#pragma unroll
                    for (int i = 0; i < 4; i++) {
                        const float e = ex2(__uint_as_float(ov[i].x) - M);
                        wg[lane + 32 * i] = e;
                        Ls = fmaf(e, __uint_as_float(ov[i].y), Ls);
                    }
                    __syncwarp();
                    if (lane == 0) mbar_arrive(mlbar);
#pragma unroll
                    for (int o = 16; o > 0; o >>= 1) Ls += __shfl_xor_sync(0xffffffffu, Ls, o);
                    if (lane == 0) wg[128] = __fdividef(1.0f, Ls);
                } else {
                    const bool giveup = *dead != 0;
                    if (!fine) {
                        const bool eager = b == kB - 1 && hkv >= kEagerHkv;
                        fine = __all_sync(0xffffffffu, mbar_test(eager ? cbar : mlbar, b & 1) || giveup);
                        okm = 0;
                        if (!fine) { (void)poll_backoff(t0, b == kB - 1 ? 50 : 300, dead); continue; }
                    }
                    const float4* ap = g_apart + ((size_t)ph * 4 + (c & 3)) * kVisPerPair * 8;
#pragma unroll
                    for (int i = 0; i < 4; i++)
                        if (!(okm >> i & 1)) ov[i] = ld_rlx4(ap + (16 * w + 4 * i) * 8 + lane);
#pragma unroll
                    for (int i = 0; i < 4; i++)
                        if (tag_ok4(ov[i], tag2)) okm |= 1u << i;
                    if (!__all_sync(0xffffffffu, okm == 15u)) {
                        if (!__any_sync(0xffffffffu, poll_backoff(t0, 30, dead))) continue;
                    }
                    mbar_wait(mlbar, b & 1, dead);
                    float a[4] = {0.f, 0.f, 0.f, 0.f};
#pragma unroll
                    for (int i = 0; i < 4; i++) {
                        const float wgt = wg[16 * w + 4 * i + (lane >> 3)];
                        a[0] = fmaf(wgt, __uint_as_float(ov[i].x), a[0]);
                        a[1] = fmaf(wgt, __uint_as_float(ov[i].y), a[1]);
                        a[2] = fmaf(wgt, __uint_as_float(ov[i].z), a[2]);
                        a[3] = fmaf(wgt, __uint_as_float(ov[i].w), a[3]);
                    }
#pragma unroll
                    for (int j = 0; j < 4; j++) {
                        a[j] += __shfl_xor_sync(0xffffffffu, a[j], 8);
                        a[j] += __shfl_xor_sync(0xffffffffu, a[j], 16);
                    }
                    if (lane < 8) *reinterpret_cast<float4*>(cb + w * 32 + 4 * lane) = make_float4(a[0], a[1], a[2], a[3]);
                }
                wbar();
                {
                    float o0 = 0.f, o1 = 0.f;
#pragma unroll
                    for (int i = 0; i < 4; i++) { o0 += cb[i * 32 + lane]; o1 += cb[(i + 4) * 32 + lane]; }
                    act[(kB + b) * kActStride + lane] = __float2bfloat16_rn((o0 + o1) * wg[128]);
                    __syncwarp();
                }
                b++;
                fine = false;
                if (!(b == kB && wo_loaded)) continue;
                task = 1;
            }
            if (task < 3) {
                const bool is_wo = task == 1;
                if (!(is_wo && wo_loaded)) {
                    mbar_wait(is_wo ? wobar : dnbar, is_wo ? 0u : dn_phase, dead);
                    rowunit_load(F, smem + (is_wo ? SM_WO : SM_WD), w, lane);
                    wo_loaded = false;
                }
                const bool extra = !is_wo && dn_left == 2;
                rowunit_publish(F, act + (is_wo ? 1 : extra ? 2 : 0) * kB * kActStride, red + 512 + w * 256,
                                is_wo ? c : kNUnitA + (extra ? G + c : c), tag2, w, lane);
                if (is_wo) wo_done = true; else dn_left--;
                if (extra) {
                    __syncwarp();
                    if (lane == 0) atomicAdd(s_dnfree, 1u);
                }
            } else if (task == 3) {
                if (c < kNFin) {
                    const bool is_s = w < 4;
                    const int q0 = is_s ? w : 32 + (w - 4), qs = is_s ? 4 : 5;
                    const float4* base = g_fin + (size_t)c * kNPart * 8 + q0 * 32 + lane;
                    uint4 v[8];
                    uint32_t spins = 0;
                    uint32_t ok = !warmed ? 0xffu : q0 + 7 * qs >= kNPart / 4 ? 0x80u : 0u;
#pragma unroll
                    for (int i = 0; i < 8; i++) v[i] = make_uint4(0u, 0u, 0u, 0u);
                    while (true) {
#pragma unroll
                        for (int i = 0; i < 8; i++)
                            if (!(ok >> i & 1)) v[i] = ld_rlx4(base + i * qs * 32);
#pragma unroll
                        for (int i = 0; i < 8; i++)
                            if (tag_ok4(v[i], tag2)) ok |= 1u << i;
                        if (__all_sync(0xffffffffu, ok == 0xffu)) break;
                        if ((++spins & 63u) == 0 && __any_sync(0xffffffffu, timed_out(t0, dead))) break;
                    }
                    float r4[4];
#pragma unroll
                    for (int j = 0; j < 4; j++) {
                        float x0 = 0.f, x1 = 0.f;
#pragma unroll
                        for (int i = 0; i < 4; i++) {
                            x0 += __uint_as_float(word_of(v[i], j));
                            x1 += __uint_as_float(word_of(v[i + 4], j));
                        }
                        r4[j] = x0 + x1;
                        r4[j] += __shfl_xor_sync(0xffffffffu, r4[j], 8);
                        r4[j] += __shfl_xor_sync(0xffffffffu, r4[j], 16);
                    }
                    float* fb = reinterpret_cast<float*>(smem + SM_XN);
                    if (warmed && lane < 8) *reinterpret_cast<float4*>(fb + w * 32 + 4 * lane) = make_float4(r4[0], r4[1], r4[2], r4[3]);
                    if (w >= 4) {
                        if (warmed) asm volatile("bar.sync 4, 160;" ::: "memory");
                        if (w == 4) {
                            const float ffn = bf16r((fb[128 + lane] + fb[160 + lane]) + (fb[192 + lane] + fb[224 + lane]) + fb[256 + lane]);
                            const float gate = bf16r(__fdividef(ffn, 1.0f + __expf(-ffn)));
                            if (warmed) {
                                fb[288 + lane] = gate;
                                asm volatile("bar.arrive 5, 160;" ::: "memory");
                            }
                        }
                    } else {
                        if (warmed) asm volatile("bar.sync 5, 160;" ::: "memory");
                        if (w == 0) {
                            const float sv = bf16r((fb[lane] + fb[32 + lane]) + (fb[64 + lane] + fb[96 + lane]));
                            if (warmed) P.out[c * 32 + lane] = __float2bfloat16_rn(xres + bf16r(sv * fb[288 + lane]));
                        }
                    }
                }
                if (warmed) break;
                warmed = true;
            } else {
                (void)poll_backoff(t0, 20, dead);
            }
        }
    } else {
        const uint32_t kbar = bar0 + 16 * warp, vbar = kbar + 8;
        const uint32_t slot = sbase + SM_SLOTS + warp * 2 * kHalfBytes;
        const unsigned char* kg = reinterpret_cast<const unsigned char*>(P.k);
        const unsigned char* vg = reinterpret_cast<const unsigned char*>(P.v);
        uint64_t pol;
        asm volatile("createpolicy.fractional.L2::evict_first.b64 %0, 1.0;" : "=l"(pol));
        int cur = warp * G + c;
        uint2 xraw[9];
        const int lnrow = 2 * (warp - (NA - 2)) + (lane >> 4);
        if (warp >= NA - 2) {
            const uint2* xr = reinterpret_cast<const uint2*>(P.x + lnrow * kD) + (lane & 15);
#pragma unroll
            for (int i = 0; i < 9; i++) xraw[i] = __ldg(xr + 16 * i);
        }
        if (lane == 0 && warp < NS) {
            mbar_init(kbar, 1);
            mbar_init(vbar, 1);
            asm volatile("fence.mbarrier_init.release.cluster;" ::: "memory");
            asm volatile("fence.proxy.async.shared::cta;" ::: "memory");
            if (warp == 0) {
                mbar_expect(kbar, kHalfBytes);
                bulk_load(slot, kg + (size_t)cur * kHalfBytes, kHalfBytes, kbar, pol);
                mbar_expect(vbar, kHalfBytes);
                bulk_load(slot + kHalfBytes, vg + (size_t)cur * kHalfBytes, kHalfBytes, vbar, pol);
            }
        }
        if (warp >= NA - 2) {
            float xv[36];
#pragma unroll
            for (int i = 0; i < 9; i++) {
                xv[4 * i] = __uint_as_float(xraw[i].x << 16);
                xv[4 * i + 1] = __uint_as_float(xraw[i].x & 0xffff0000u);
                xv[4 * i + 2] = __uint_as_float(xraw[i].y << 16);
                xv[4 * i + 3] = __uint_as_float(xraw[i].y & 0xffff0000u);
            }
            float s0 = 0.f, s1 = 0.f;
#pragma unroll
            for (int i = 0; i < 18; i++) { s0 += xv[2 * i]; s1 += xv[2 * i + 1]; }
            float sum = s0 + s1;
#pragma unroll
            for (int o = 8; o > 0; o >>= 1) sum += __shfl_xor_sync(0xffffffffu, sum, o);
            const float mean = sum * (1.0f / kD);
            s0 = s1 = 0.f;
#pragma unroll
            for (int i = 0; i < 18; i++) {
                const float d0 = xv[2 * i] - mean, d1 = xv[2 * i + 1] - mean;
                s0 = fmaf(d0, d0, s0); s1 = fmaf(d1, d1, s1);
            }
            float sq = s0 + s1;
#pragma unroll
            for (int o = 8; o > 0; o >>= 1) sq += __shfl_xor_sync(0xffffffffu, sq, o);
            const float mb = bf16r(mean);
            const float den = bf16r(sqrtf(bf16r(bf16r(sq * (1.0f / kD)) + 1e-5f)));
            uint2* xo = reinterpret_cast<uint2*>(smem + SM_XN + lnrow * kXnStride * 2) + (lane & 15);
#pragma unroll
            for (int i = 0; i < 9; i++) {
                xo[16 * i] = make_uint2(
                    pack_bf16(__fdividef(bf16r(xv[4 * i] - mb), den), __fdividef(bf16r(xv[4 * i + 1] - mb), den)),
                    pack_bf16(__fdividef(bf16r(xv[4 * i + 2] - mb), den), __fdividef(bf16r(xv[4 * i + 3] - mb), den)));
            }
        }
        __syncwarp();
        if (warp == 0) asm volatile("bar.arrive 0, %0;" ::"n"(kThreads) : "memory");
        uint32_t tag2 = 0;
        unsigned int ticket = 0;
        const unsigned char* ks = smem + SM_SLOTS + warp * 2 * kHalfBytes;
        const unsigned char* kA = ks + g * 256 + t * 16 + 64 * (g & 1);
        const unsigned char* kBp = ks + g * 256 + t * 16 + 64 * ((g & 1) ^ 1);
        const uint32_t vrow = slot + kHalfBytes + (8 * (lane >> 4) + (lane & 7)) * 256 + ((lane >> 3) & 1) * 128;
        const uint32_t vrot = 32u * ((lane & 7) >> 1);
        const unsigned char* qA = smem + SM_Q + warp * 1536 + (g >> 2) * 256 + t * 16 + 64 * ((g >> 1) & 1) + 4 * (g & 1);
        const unsigned char* qB = smem + SM_Q + warp * 1536 + (g >> 2) * 256 + t * 16 + 64 * (((g >> 1) & 1) ^ 1) + 4 * (g & 1);
        float* ostage = reinterpret_cast<float*>(smem + SM_Q + warp * 1536 + 512);
        const float kLog2e = 1.4426950408889634f;
        const bool own = (g >> 1) == t;
        const int psrc = 8 * t + 2 * (g & 1);
        uint32_t phase = 0;
        unsigned exh = 0;
        ulonglong2 q0, q1;
        uint32_t tag32 = 0;
        bool live = false, setup = warp != 0;
        while (true) {
            const int pair = cur >> 7, tile = cur & 127;
            if (setup) {
                if (warp == 0) {
                    asm volatile("bar.sync 3, 64;" ::: "memory");
                } else {
                    asm volatile("bar.sync 0, %0;" ::"n"(kThreads) : "memory");
                    if (warp >= NS) break;
                    mbar_wait(kbar - 16, 0, dead);
                    if (lane == 0) {
                        mbar_expect(kbar, kHalfBytes);
                        bulk_load(slot, kg + (size_t)cur * kHalfBytes, kHalfBytes, kbar, pol);
                        mbar_expect(vbar, kHalfBytes);
                        bulk_load(slot + kHalfBytes, vg + (size_t)cur * kHalfBytes, kHalfBytes, vbar, pol);
                    }
                }
                tag32 = *s_tag;
                tag2 = tag32 & 3u;
                if (lane == 0) ticket = take_ticket();
                q0 = ld_rlx2x64(g_qx + pair * 64 + lane);
                q1 = ld_rlx2x64(g_qx + pair * 64 + 32 + lane);
                setup = false;
                live = true;
            }
            if (live) {
                const uint32_t t0 = (uint32_t)clock();
                while (!__all_sync(0xffffffffu, (uint32_t)(q0.x >> 32) == tag32 && (uint32_t)(q0.y >> 32) == tag32 &&
                                                   (uint32_t)(q1.x >> 32) == tag32 && (uint32_t)(q1.y >> 32) == tag32)) {
                    if (__any_sync(0xffffffffu, poll_backoff(t0, 50, dead))) break;
                    q0 = ld_rlx2x64(g_qx + pair * 64 + lane);
                    q1 = ld_rlx2x64(g_qx + pair * 64 + 32 + lane);
                }
                uint2* qd = reinterpret_cast<uint2*>(smem + SM_Q + warp * 1536) + lane;
                qd[0] = make_uint2((uint32_t)q0.x, (uint32_t)q0.y);
                qd[32] = make_uint2((uint32_t)q1.x, (uint32_t)q1.y);
                __syncwarp();
            }
            uint32_t Q[4][2];
#pragma unroll
            for (int i = 0; i < 4; i++) {
                const unsigned char* qp = ((i & 1) ? qB : qA) + (i >> 1) * 128;
                Q[i][0] = *reinterpret_cast<const uint32_t*>(qp);
                Q[i][1] = *reinterpret_cast<const uint32_t*>(qp + 8);
            }
            if (live) mbar_wait(kbar, phase, dead);
            float s[4][2];
#pragma unroll
            for (int u = 0; u < 4; u++) {
                float cc[2][4];
#pragma unroll
                for (int hh = 0; hh < 2; hh++) {
                    const int off = u * 4096 + hh * 2048;
                    const uint4 k0 = *reinterpret_cast<const uint4*>(kA + off), k1 = *reinterpret_cast<const uint4*>(kBp + off);
                    const uint4 k2 = *reinterpret_cast<const uint4*>(kA + off + 128), k3 = *reinterpret_cast<const uint4*>(kBp + off + 128);
                    cc[hh][0] = cc[hh][1] = cc[hh][2] = cc[hh][3] = 0.f;
                    mma16816(cc[hh], k0.x, k0.y, k0.z, k0.w, Q[0][0], Q[0][1]);
                    mma16816(cc[hh], k1.x, k1.y, k1.z, k1.w, Q[1][0], Q[1][1]);
                    mma16816(cc[hh], k2.x, k2.y, k2.z, k2.w, Q[2][0], Q[2][1]);
                    mma16816(cc[hh], k3.x, k3.y, k3.z, k3.w, Q[3][0], Q[3][1]);
                }
                uint32_t pk = pack_bf16(cc[0][0] + cc[0][3], cc[1][0] + cc[1][3]);
                pk = pack_bf16(__uint_as_float(pk << 16) * 0.08838834764831845f,
                               __uint_as_float(pk & 0xffff0000u) * 0.08838834764831845f);
                s[u][0] = __uint_as_float(pk << 16);
                s[u][1] = __uint_as_float(pk & 0xffff0000u);
            }
            float mx = fmaxf(fmaxf(fmaxf(s[0][0], s[0][1]), fmaxf(s[1][0], s[1][1])),
                             fmaxf(fmaxf(s[2][0], s[2][1]), fmaxf(s[3][0], s[3][1])));
            mx = fmaxf(mx, __shfl_xor_sync(0xffffffffu, mx, 5));
            mx = fmaxf(mx, __shfl_xor_sync(0xffffffffu, mx, 8));
            mx = fmaxf(mx, __shfl_xor_sync(0xffffffffu, mx, 16));
            int nxt = cur;
            bool more = true;
            if (live) {
                nxt = (int)(__shfl_sync(0xffffffffu, ticket, 0) & (unsigned)(kNVis - 1)) + NS * G;
                more = nxt < kNVis;
                if (more) {
                    if (lane == 0) {
                        mbar_expect(kbar, kHalfBytes);
                        bulk_load(slot, kg + (size_t)nxt * kHalfBytes, kHalfBytes, kbar, pol);
                    }
                    q0 = ld_rlx2x64(g_qx + (nxt >> 7) * 64 + lane);
                    q1 = ld_rlx2x64(g_qx + (nxt >> 7) * 64 + 32 + lane);
                } else if (!critical) {
                    if (lane == 0) exh = atomicAdd(s_exh, 1u);
                    exh = __shfl_sync(0xffffffffu, exh, 0);
                    if (exh == 1 && hasA) issue_rowunit(sbase + SM_WO, P.wo, c, wobar, lane, pol);
                }
            }
            const uint32_t mtag = tagf(mx * kLog2e, tag2);
            const float mc = __uint_as_float(mtag);
            uint32_t pb[4][2];
            float l = 0.f;
#pragma unroll
            for (int u = 0; u < 4; u++) {
                const float p0 = ex2(fmaf(s[u][0], kLog2e, -mc));
                const float p1 = ex2(fmaf(s[u][1], kLog2e, -mc));
                l += p0 + p1;
                const uint32_t pk = pack_bf16(p0, p1);
                const uint32_t x = __shfl_sync(0xffffffffu, pk, psrc), y = __shfl_sync(0xffffffffu, pk, psrc + 5);
                pb[u][0] = own ? __byte_perm(x, y, 0x5410) : 0u;
                pb[u][1] = own ? __byte_perm(x, y, 0x7632) : 0u;
            }
            l += __shfl_xor_sync(0xffffffffu, l, 5);
            l += __shfl_xor_sync(0xffffffffu, l, 8);
            l += __shfl_xor_sync(0xffffffffu, l, 16);
            if (live) mbar_wait(vbar, phase, dead);
            float o[8][4];
#pragma unroll
            for (int j = 0; j < 8; j++) o[j][0] = o[j][1] = o[j][2] = o[j][3] = 0.f;
#pragma unroll
            for (int u = 0; u < 4; u++) {
#pragma unroll
                for (int j = 0; j < 8; j++) {
                    uint32_t a0, a1, a2, a3;
                    asm volatile("ldmatrix.sync.aligned.m8n8.x4.trans.shared.b16 {%0,%1,%2,%3}, [%4];"
                                 : "=r"(a0), "=r"(a1), "=r"(a2), "=r"(a3)
                                 : "r"(vrow + u * 4096 + (j & 1) * 16 + ((32u * (j >> 1)) ^ vrot)) : "memory");
                    mma16816(o[j], a0, a1, a2, a3, pb[u][0], pb[u][1]);
                }
            }
            float r[4][4], f[2][4];
#pragma unroll
            for (int jj = 0; jj < 4; jj++) {
                const int j = (jj & 1) + 4 * (jj >> 1);
#pragma unroll
                for (int cc = 0; cc < 4; cc++) r[jj][cc] = o[j][cc] + __shfl_xor_sync(0xffffffffu, o[j ^ 2][cc], 1);
            }
            if (lane == 0 && more && live) {
                mbar_expect(vbar, kHalfBytes);
                bulk_load(slot + kHalfBytes, vg + (size_t)nxt * kHalfBytes, kHalfBytes, vbar, pol);
                ticket = take_ticket();
            }
#pragma unroll
            for (int j = 0; j < 2; j++) {
#pragma unroll
                for (int cc = 0; cc < 4; cc++) {
                    f[j][cc] = r[j][cc] + __shfl_xor_sync(0xffffffffu, r[j + 2][cc], 2);
                    ostage[(cc & 1) * 128 + (cc >> 1) * 64 + 16 * t + 8 * j + g] = f[j][cc];
                }
            }
            __syncwarp();
            const float4 f0 = *reinterpret_cast<const float4*>(ostage + 4 * lane);
            const float4 f1 = *reinterpret_cast<const float4*>(ostage + 128 + 4 * lane);
            if (live) {
                float4* dst = g_apart + (((size_t)(pair * 2) * 4 + (lane >> 3)) * kVisPerPair + tile) * 8 + (lane & 7);
                st_rlx4(dst, tagf(f0.x, tag2), tagf(f0.y, tag2), tagf(f0.z, tag2), tagf(f0.w, tag2));
                st_rlx4(dst + 4 * kVisPerPair * 8, tagf(f1.x, tag2), tagf(f1.y, tag2), tagf(f1.z, tag2), tagf(f1.w, tag2));
                if ((lane & ~2) == 0) st_rlx2(g_aml + (size_t)(pair * 2 + (lane >> 1)) * kVisPerPair + tile, mtag, tagf(l, tag2));
                if (!more) {
                    if (!critical && exh == 0) {
                        if (twoF) {
                            const uint32_t t0 = (uint32_t)clock();
                            while (*reinterpret_cast<volatile unsigned int*>(s_dnfree) < NW)
                                if (poll_backoff(t0, 100, dead)) break;
                        }
                        issue_rowunit(sbase + SM_WD, P.wd, c, dnbar, lane, pol);
                    }
                    break;
                }
                cur = nxt;
                phase ^= 1u;
            } else {
                if (__float_as_uint(f0.x + f1.y + l) == 0x7fc12345u && *dead == 0x5a5a5a5a) *s_exh = 0;
                setup = true;
            }
        }
    }
}

constexpr int kFbSplit = 16;
__device__ float fb_q[kB * kHQ * kDH], fb_h[kB * kF], fb_o[kB * kHQ * kDH];
__device__ float fb_m[kB * kHQ * kFbSplit], fb_l[kB * kHQ * kFbSplit], fb_p[kB * kHQ * kFbSplit * kDH];

__global__ void __launch_bounds__(128) fb_proj_kernel(const Params P) {
    __shared__ float xn[kB][kD];
    const int warp = threadIdx.x >> 5, lane = threadIdx.x & 31;
    float sum = 0.f, sq = 0.f;
    for (int i = lane; i < kD; i += 32) sum += __bfloat162float(P.x[warp * kD + i]);
    for (int o = 16; o > 0; o >>= 1) sum += __shfl_xor_sync(0xffffffffu, sum, o);
    const float mean = sum * (1.0f / kD);
    for (int i = lane; i < kD; i += 32) { const float d = __bfloat162float(P.x[warp * kD + i]) - mean; sq += d * d; }
    for (int o = 16; o > 0; o >>= 1) sq += __shfl_xor_sync(0xffffffffu, sq, o);
    const float mb = bf16r(mean), den = bf16r(sqrtf(bf16r(bf16r(sq * (1.0f / kD)) + 1e-5f)));
    for (int i = lane; i < kD; i += 32) xn[warp][i] = bf16r(bf16r(__bfloat162float(P.x[warp * kD + i]) - mb) / den);
    __syncthreads();
    const int n = blockIdx.x * 128 + threadIdx.x;
    const bool isq = n < kHQ * kDH;
    const int col = isq ? n : n - kHQ * kDH, ld = isq ? kHQ * kDH : kF;
    const __nv_bfloat16* w0 = (isq ? P.wq : P.wg) + col;
    float a[kB] = {0.f, 0.f, 0.f, 0.f}, u[kB] = {0.f, 0.f, 0.f, 0.f};
    for (int k = 0; k < kD; k++) {
        const float x0 = __bfloat162float(w0[(size_t)k * ld]);
        const float x1 = isq ? 0.f : __bfloat162float(P.wu[(size_t)k * kF + col]);
        for (int b = 0; b < kB; b++) { a[b] = fmaf(xn[b][k], x0, a[b]); u[b] = fmaf(xn[b][k], x1, u[b]); }
    }
    for (int b = 0; b < kB; b++) {
        const float gv = bf16r(a[b]);
        if (isq) fb_q[b * kHQ * kDH + col] = gv;
        else fb_h[b * kF + col] = bf16r((gv > 0.f ? gv : 0.f) * bf16r(u[b]));
    }
}
__global__ void __launch_bounds__(128) fb_attn_kernel(const Params P) {
    constexpr int kKeys = kSK / kFbSplit;
    __shared__ float sc[kKeys], red[4];
    const int bh = blockIdx.y, sp = blockIdx.x, warp = threadIdx.x >> 5, lane = threadIdx.x & 31;
    const size_t base = ((size_t)((bh / kHQ) * kHKV + (bh % kHQ) / 2) * kSK + (size_t)sp * kKeys) * kDH;
    float q[4];
    for (int i = 0; i < 4; i++) q[i] = fb_q[bh * kDH + 4 * lane + i];
    float mx = -INFINITY;
    for (int k = warp; k < kKeys; k += 4) {
        float s = 0.f;
        for (int i = 0; i < 4; i++) s = fmaf(q[i], __bfloat162float(P.k[base + (size_t)k * kDH + 4 * lane + i]), s);
        for (int o = 16; o > 0; o >>= 1) s += __shfl_xor_sync(0xffffffffu, s, o);
        s = bf16r(bf16r(s) * 0.08838834764831845f);
        if (lane == 0) sc[k] = s;
        mx = fmaxf(mx, s);
    }
    if (lane == 0) red[warp] = mx;
    __syncthreads();
    mx = fmaxf(fmaxf(red[0], red[1]), fmaxf(red[2], red[3]));
    float l = 0.f, acc = 0.f;
    for (int k = 0; k < kKeys; k++) {
        const float p = __expf(sc[k] - mx);
        l += p;
        acc = fmaf(bf16r(p), __bfloat162float(P.v[base + (size_t)k * kDH + threadIdx.x]), acc);
    }
    fb_p[(bh * kFbSplit + sp) * kDH + threadIdx.x] = acc;
    if (threadIdx.x == 0) { fb_m[bh * kFbSplit + sp] = mx; fb_l[bh * kFbSplit + sp] = l; }
}
__global__ void __launch_bounds__(128) fb_combine_kernel() {
    const int bh = blockIdx.x;
    float M = -INFINITY, L = 0.f, o = 0.f;
    for (int i = 0; i < kFbSplit; i++) M = fmaxf(M, fb_m[bh * kFbSplit + i]);
    for (int i = 0; i < kFbSplit; i++) {
        const float e = __expf(fb_m[bh * kFbSplit + i] - M);
        L = fmaf(e, fb_l[bh * kFbSplit + i], L);
        o = fmaf(e, fb_p[(bh * kFbSplit + i) * kDH + threadIdx.x], o);
    }
    fb_o[bh * kDH + threadIdx.x] = bf16r(o / L);
}
__global__ void __launch_bounds__(256) fb_out_kernel(const Params P) {
    __shared__ float rs[8][32], rf[8][32];
    const int b = blockIdx.y, col = blockIdx.x * 32 + (threadIdx.x & 31), part = threadIdx.x >> 5;
    float s = 0.f, f = 0.f;
    for (int k = part; k < kHQ * kDH; k += 8) s = fmaf(fb_o[b * kHQ * kDH + k], __bfloat162float(P.wo[(size_t)k * kD + col]), s);
    for (int k = part; k < kF; k += 8) f = fmaf(fb_h[b * kF + k], __bfloat162float(P.wd[(size_t)k * kD + col]), f);
    rs[part][threadIdx.x & 31] = s;
    rf[part][threadIdx.x & 31] = f;
    __syncthreads();
    if (part == 0) {
        s = f = 0.f;
        for (int i = 0; i < 8; i++) { s += rs[i][threadIdx.x]; f += rf[i][threadIdx.x]; }
        s = bf16r(s);
        f = bf16r(f);
        const float gate = bf16r(f / (1.0f + __expf(-f)));
        P.out[b * kD + col] = __float2bfloat16_rn(__bfloat162float(P.x[b * kD + col]) + bf16r(s * gate));
    }
}

}


extern "C" void kernel_launch(void* const* d_in, const int* in_sizes, int n_in, void* d_out, int out_size) {
    (void)in_sizes; (void)n_in; (void)out_size;
    static int grid = 0;
    if (grid == 0) {
        int dev = 0, sms = 0, smem = 0, coop = 0, occ = 0;
        cudaGetDevice(&dev);
        cudaDeviceGetAttribute(&sms, cudaDevAttrMultiProcessorCount, dev);
        cudaDeviceGetAttribute(&smem, cudaDevAttrMaxSharedMemoryPerBlockOptin, dev);
        cudaDeviceGetAttribute(&coop, cudaDevAttrCooperativeLaunch, dev);
        grid = -1;
        if (coop && sms > rk::kNUnitA && smem >= rk::SM_TOTAL &&
            cudaFuncSetAttribute(rk::fused_decode_kernel, cudaFuncAttributeMaxDynamicSharedMemorySize, rk::SM_TOTAL) == cudaSuccess &&
            cudaOccupancyMaxActiveBlocksPerMultiprocessor(&occ, rk::fused_decode_kernel, rk::kThreads, rk::SM_TOTAL) == cudaSuccess &&
            occ >= 1)
            grid = sms < rk::kNUnitF ? sms : rk::kNUnitF;
        (void)cudaGetLastError();
    }
    rk::Params P;
    P.x = (const __nv_bfloat16*)d_in[0];
    P.k = (const __nv_bfloat16*)d_in[1];
    P.v = (const __nv_bfloat16*)d_in[2];
    P.wq = (const __nv_bfloat16*)d_in[3];
    P.wo = (const __nv_bfloat16*)d_in[4];
    P.wg = (const __nv_bfloat16*)d_in[6];
    P.wu = (const __nv_bfloat16*)d_in[7];
    P.wd = (const __nv_bfloat16*)d_in[8];
    P.out = (__nv_bfloat16*)d_out;
    if (grid > 0) {
        void* args[] = {&P};
        cudaLaunchCooperativeKernel((const void*)rk::fused_decode_kernel, dim3(grid), dim3(rk::kThreads), args, rk::SM_TOTAL, 0);
    } else {
        rk::fb_proj_kernel<<<(rk::kHQ * rk::kDH + rk::kF) / 128, 128>>>(P);
        rk::fb_attn_kernel<<<dim3(rk::kFbSplit, rk::kB * rk::kHQ), 128>>>(P);
        rk::fb_combine_kernel<<<rk::kB * rk::kHQ, 128>>>();
        rk::fb_out_kernel<<<dim3(rk::kD / 32, rk::kB), 256>>>(P);
    }
}
```
